```python
import torch

def _softmax(x, axis=-1):
    return torch.softmax(x, dim=axis)
def _gelu(x):
    return torch.nn.functional.gelu(x, approximate="tanh")
def _silu(x):
    return torch.nn.functional.silu(x)
def _sigmoid(x):
    return torch.sigmoid(x)
def _layernorm(x, axis=-1, eps=1e-5):
    m = x.mean(dim=axis, keepdim=True)
    v = x.var(dim=axis, keepdim=True, unbiased=False)
    return (x - m) / torch.sqrt(v + eps)
def _scatter_add(tgt, idx, src, axis=0):
    return tgt.clone().index_add_(axis, idx, src)
def _segment_sum(src, seg, n):
    out = torch.zeros((n,) + src.shape[1:], dtype=src.dtype)
    return out.index_add_(0, seg, src)
def _pad(x, pw):
    flat = tuple(v for pair in reversed(pw) for v in pair)
    return torch.nn.functional.pad(x, flat)

kernel_name = 'parallel_sum__grouped_kv_mqa__geglu_ffn__prompt'

def setup_inputs():

    _w = (lambda a: (lambda t: t.to(torch.bfloat16) if t.is_floating_point() else t)(torch.as_tensor(a)))
    def _A_setup():
        B, S, D, H = 1, 2048, 640, 32
        Dh = D // H
        return {
            "x": _w((lambda *s: torch.randn(*s, dtype=torch.bfloat16) * 0.05)(B, S, D)),
            "wq": _w((lambda *s: torch.randn(*s, dtype=torch.bfloat16) * 0.2)(D, H * Dh)),
            "wk": _w((lambda *s: torch.randn(*s, dtype=torch.bfloat16) * 0.2)(D, Dh)),
            "wv": _w((lambda *s: torch.randn(*s, dtype=torch.bfloat16) * 0.1)(D, Dh)),
            "wo": _w((lambda *s: torch.randn(*s, dtype=torch.bfloat16) * 0.1)(H * Dh, D)),
        }
    _A_in = _A_setup()

    def _B_setup():
        B, S, D, F = 1, 2048, 640, 1536
        return {
            "x": _w((lambda *s: torch.randn(*s, dtype=torch.bfloat16) * 0.05)(B, S, D)),
            "w_gate": _w((lambda *s: torch.randn(*s, dtype=torch.bfloat16) * 0.1)(D, F)),
            "w_up": _w((lambda *s: torch.randn(*s, dtype=torch.bfloat16) * 0.1)(D, F)),
            "w_down": _w((lambda *s: torch.randn(*s, dtype=torch.bfloat16) * 0.1)(F, D)),
        }
    _B_in = _B_setup()

    return {
        "A_x": _A_in["x"],
        "A_wq": _A_in["wq"],
        "A_wk": _A_in["wk"],
        "A_wv": _A_in["wv"],
        "A_wo": _A_in["wo"],
        "B_x": _B_in["x"],
        "B_w_gate": _B_in["w_gate"],
        "B_w_up": _B_in["w_up"],
        "B_w_down": _B_in["w_down"],
    }

def reference(A_x, A_wq, A_wk, A_wv, A_wo, B_x, B_w_gate, B_w_up, B_w_down):
    def _A_ref(x, wq, wk, wv, wo):
        B, S, D = x.shape
        H = 32
        Dh = D // H
        q = (lambda x, *d: x.permute(*d))((x @ wq).reshape(B, S, H, Dh), 0, 2, 1, 3)
        k = x @ wk
        v = x @ wv
        scores = torch.einsum("bhqd,bkd->bhqk", q, k) * (Dh ** -0.5)
        p = _softmax(scores, axis=-1)
        o = torch.einsum("bhqk,bkd->bhqd", p, v)
        return (lambda x, *d: x.permute(*d))(o, 0, 2, 1, 3).reshape(B, S, H * Dh) @ wo

    def _B_ref(x, w_gate, w_up, w_down):
        return (_gelu(x @ w_gate) * (x @ w_up)) @ w_down

    x = A_x
    xn = _layernorm(x, axis=-1)
    return x + _A_ref(xn, A_wq, A_wk, A_wv, A_wo) + _B_ref(xn, B_w_gate, B_w_up, B_w_down)
```

```cpp
#include <cuda_runtime.h>
#include <cuda_bf16.h>
#include <cuda.h>
#include <stdint.h>
typedef __nv_bfloat16 bf16;
__device__ __forceinline__ uint32_t smem_u32(const void* p) { return (uint32_t)__cvta_generic_to_shared(p); }
__device__ __forceinline__ void mbar_init(uint32_t bar, uint32_t cnt) { asm volatile("mbarrier.init.shared::cta.b64 [%0], %1;" :: "r"(bar), "r"(cnt) : "memory"); }
__device__ __forceinline__ void mbar_expect_tx(uint32_t bar, uint32_t bytes) { asm volatile("mbarrier.arrive.expect_tx.shared::cta.b64 _, [%0], %1;" :: "r"(bar), "r"(bytes) : "memory"); }
__device__ __forceinline__ void mbar_arrive(uint32_t bar) { asm volatile("mbarrier.arrive.shared::cta.b64 _, [%0];" :: "r"(bar) : "memory"); }
__device__ __forceinline__ void mbar_wait(uint32_t bar, uint32_t parity) {
  asm volatile("{\n.reg .pred p, q;\n.reg .u32 c;\nmov.u32 c, 0;\nLAB_WAIT:\nmbarrier.try_wait.parity.shared::cta.b64 p, [%0], %1;\n@p bra DONE;\n"
               "add.u32 c, c, 1;\nsetp.lt.u32 q, c, 4000000;\n@q bra LAB_WAIT;\ntrap;\nDONE:\n}\n" :: "r"(bar), "r"(parity) : "memory");
}
__device__ __forceinline__ void tma2d(uint32_t dst, const CUtensorMap* tm, int c0, int c1, uint32_t bar) {
  asm volatile("cp.async.bulk.tensor.2d.shared::cluster.global.mbarrier::complete_tx::bytes [%0], [%1, {%2, %3}], [%4];" :: "r"(dst), "l"(tm), "r"(c0), "r"(c1), "r"(bar) : "memory");
}
__device__ __forceinline__ void pdl_wait() { asm volatile("griddepcontrol.wait;" ::: "memory"); }
__device__ __forceinline__ void pdl_launch() { asm volatile("griddepcontrol.launch_dependents;" ::: "memory"); }
__device__ __forceinline__ void bulk_g2s(uint32_t dst, const void* src, uint32_t bytes, uint32_t bar) {
  asm volatile("cp.async.bulk.shared::cluster.global.mbarrier::complete_tx::bytes [%0], [%1], %2, [%3];" :: "r"(dst), "l"(src), "r"(bytes), "r"(bar) : "memory");
}
__device__ __forceinline__ void wg_fence() { asm volatile("wgmma.fence.sync.aligned;" ::: "memory"); }
__device__ __forceinline__ void wg_commit() { asm volatile("wgmma.commit_group.sync.aligned;" ::: "memory"); }
template <int N> __device__ __forceinline__ void wg_wait() { asm volatile("wgmma.wait_group.sync.aligned %0;" :: "n"(N) : "memory"); }
template <int N> __device__ __forceinline__ void reg_fence(float (&d)[N]) {
#pragma unroll
  for (int i = 0; i < N; i++) asm volatile("" : "+f"(d[i]) :: "memory");
}
template <int N> __device__ __forceinline__ void reg_fence(uint32_t (&d)[N]) {
#pragma unroll
  for (int i = 0; i < N; i++) asm volatile("" : "+r"(d[i]) :: "memory");
}
__device__ __forceinline__ uint64_t mk_desc(uint32_t addr, uint32_t lbo, uint32_t sbo, uint32_t swz) {
  return (uint64_t)((addr & 0x3FFFF) >> 4) | ((uint64_t)(lbo >> 4) << 16) | ((uint64_t)(sbo >> 4) << 32) | ((uint64_t)swz << 62);
}
__device__ __forceinline__ uint32_t pack_bf16(float lo, float hi) {
  uint32_t r; asm("cvt.rn.bf16x2.f32 %0, %1, %2;" : "=r"(r) : "f"(hi), "f"(lo)); return r;
}
__device__ __forceinline__ float ex2(float x) { float y; asm("ex2.approx.ftz.f32 %0, %1;" : "=f"(y) : "f"(x)); return y; }
__device__ __forceinline__ void tma2d_mc(uint32_t dst, const CUtensorMap* tm, int c0, int c1, uint32_t bar) {
  asm volatile("cp.async.bulk.tensor.2d.shared::cluster.global.mbarrier::complete_tx::bytes.multicast::cluster [%0], [%1, {%2, %3}], [%4], %5;"
               :: "r"(dst), "l"(tm), "r"(c0), "r"(c1), "r"(bar), "h"((uint16_t)3) : "memory");
}
__device__ __forceinline__ void cluster_sync() { asm volatile("barrier.cluster.arrive.relaxed.aligned;\nbarrier.cluster.wait.aligned;" ::: "memory"); }
__device__ __forceinline__ void mbar_arrive_both(uint32_t bar) {
  asm volatile("{\n.reg .b32 a, b;\nmapa.shared::cluster.u32 a, %0, 0;\nmapa.shared::cluster.u32 b, %0, 1;\n"
               "mbarrier.arrive.shared::cluster.b64 _, [a];\nmbarrier.arrive.shared::cluster.b64 _, [b];\n}" :: "r"(bar) : "memory");
}
#define TL(k)
__device__ __forceinline__ void wg_rs_n64_first(float (&d)[32], uint32_t a0, uint32_t a1, uint32_t a2, uint32_t a3, uint64_t desc) {
  asm volatile("{\n.reg .pred p;\nsetp.ne.b32 p, 0, 0;\n"
    "wgmma.mma_async.sync.aligned.m64n64k16.f32.bf16.bf16 {%0, %1, %2, %3, %4, %5, %6, %7, %8, %9, %10, %11, %12, %13, %14, %15, %16, %17, %18, %19, %20, %21, %22, %23, %24, %25, %26, %27, %28, %29, %30, %31}, {%32,%33,%34,%35}, %36, p, 1, 1, 0;\n}\n"
    : "=f"(d[0]), "=f"(d[1]), "=f"(d[2]), "=f"(d[3]), "=f"(d[4]), "=f"(d[5]), "=f"(d[6]), "=f"(d[7]), "=f"(d[8]), "=f"(d[9]), "=f"(d[10]), "=f"(d[11]), "=f"(d[12]), "=f"(d[13]), "=f"(d[14]), "=f"(d[15]), "=f"(d[16]), "=f"(d[17]), "=f"(d[18]), "=f"(d[19]), "=f"(d[20]), "=f"(d[21]), "=f"(d[22]), "=f"(d[23]), "=f"(d[24]), "=f"(d[25]), "=f"(d[26]), "=f"(d[27]), "=f"(d[28]), "=f"(d[29]), "=f"(d[30]), "=f"(d[31])
    : "r"(a0), "r"(a1), "r"(a2), "r"(a3), "l"(desc));
}
__device__ __forceinline__ void wg_rs_n64_acc(float (&d)[32], uint32_t a0, uint32_t a1, uint32_t a2, uint32_t a3, uint64_t desc) {
  asm volatile("{\n.reg .pred p;\nsetp.ne.b32 p, 1, 0;\n"
    "wgmma.mma_async.sync.aligned.m64n64k16.f32.bf16.bf16 {%0, %1, %2, %3, %4, %5, %6, %7, %8, %9, %10, %11, %12, %13, %14, %15, %16, %17, %18, %19, %20, %21, %22, %23, %24, %25, %26, %27, %28, %29, %30, %31}, {%32,%33,%34,%35}, %36, p, 1, 1, 0;\n}\n"
    : "+f"(d[0]), "+f"(d[1]), "+f"(d[2]), "+f"(d[3]), "+f"(d[4]), "+f"(d[5]), "+f"(d[6]), "+f"(d[7]), "+f"(d[8]), "+f"(d[9]), "+f"(d[10]), "+f"(d[11]), "+f"(d[12]), "+f"(d[13]), "+f"(d[14]), "+f"(d[15]), "+f"(d[16]), "+f"(d[17]), "+f"(d[18]), "+f"(d[19]), "+f"(d[20]), "+f"(d[21]), "+f"(d[22]), "+f"(d[23]), "+f"(d[24]), "+f"(d[25]), "+f"(d[26]), "+f"(d[27]), "+f"(d[28]), "+f"(d[29]), "+f"(d[30]), "+f"(d[31])
    : "r"(a0), "r"(a1), "r"(a2), "r"(a3), "l"(desc));
}
__device__ __forceinline__ void wg_rs_n128_first(float (&d)[64], uint32_t a0, uint32_t a1, uint32_t a2, uint32_t a3, uint64_t desc) {
  asm volatile("{\n.reg .pred p;\nsetp.ne.b32 p, 0, 0;\n"
    "wgmma.mma_async.sync.aligned.m64n128k16.f32.bf16.bf16 {%0, %1, %2, %3, %4, %5, %6, %7, %8, %9, %10, %11, %12, %13, %14, %15, %16, %17, %18, %19, %20, %21, %22, %23, %24, %25, %26, %27, %28, %29, %30, %31, %32, %33, %34, %35, %36, %37, %38, %39, %40, %41, %42, %43, %44, %45, %46, %47, %48, %49, %50, %51, %52, %53, %54, %55, %56, %57, %58, %59, %60, %61, %62, %63}, {%64,%65,%66,%67}, %68, p, 1, 1, 0;\n}\n"
    : "=f"(d[0]), "=f"(d[1]), "=f"(d[2]), "=f"(d[3]), "=f"(d[4]), "=f"(d[5]), "=f"(d[6]), "=f"(d[7]), "=f"(d[8]), "=f"(d[9]), "=f"(d[10]), "=f"(d[11]), "=f"(d[12]), "=f"(d[13]), "=f"(d[14]), "=f"(d[15]), "=f"(d[16]), "=f"(d[17]), "=f"(d[18]), "=f"(d[19]), "=f"(d[20]), "=f"(d[21]), "=f"(d[22]), "=f"(d[23]), "=f"(d[24]), "=f"(d[25]), "=f"(d[26]), "=f"(d[27]), "=f"(d[28]), "=f"(d[29]), "=f"(d[30]), "=f"(d[31]), "=f"(d[32]), "=f"(d[33]), "=f"(d[34]), "=f"(d[35]), "=f"(d[36]), "=f"(d[37]), "=f"(d[38]), "=f"(d[39]), "=f"(d[40]), "=f"(d[41]), "=f"(d[42]), "=f"(d[43]), "=f"(d[44]), "=f"(d[45]), "=f"(d[46]), "=f"(d[47]), "=f"(d[48]), "=f"(d[49]), "=f"(d[50]), "=f"(d[51]), "=f"(d[52]), "=f"(d[53]), "=f"(d[54]), "=f"(d[55]), "=f"(d[56]), "=f"(d[57]), "=f"(d[58]), "=f"(d[59]), "=f"(d[60]), "=f"(d[61]), "=f"(d[62]), "=f"(d[63])
    : "r"(a0), "r"(a1), "r"(a2), "r"(a3), "l"(desc));
}
__device__ __forceinline__ void wg_rs_n128_acc(float (&d)[64], uint32_t a0, uint32_t a1, uint32_t a2, uint32_t a3, uint64_t desc) {
  asm volatile("{\n.reg .pred p;\nsetp.ne.b32 p, 1, 0;\n"
    "wgmma.mma_async.sync.aligned.m64n128k16.f32.bf16.bf16 {%0, %1, %2, %3, %4, %5, %6, %7, %8, %9, %10, %11, %12, %13, %14, %15, %16, %17, %18, %19, %20, %21, %22, %23, %24, %25, %26, %27, %28, %29, %30, %31, %32, %33, %34, %35, %36, %37, %38, %39, %40, %41, %42, %43, %44, %45, %46, %47, %48, %49, %50, %51, %52, %53, %54, %55, %56, %57, %58, %59, %60, %61, %62, %63}, {%64,%65,%66,%67}, %68, p, 1, 1, 0;\n}\n"
    : "+f"(d[0]), "+f"(d[1]), "+f"(d[2]), "+f"(d[3]), "+f"(d[4]), "+f"(d[5]), "+f"(d[6]), "+f"(d[7]), "+f"(d[8]), "+f"(d[9]), "+f"(d[10]), "+f"(d[11]), "+f"(d[12]), "+f"(d[13]), "+f"(d[14]), "+f"(d[15]), "+f"(d[16]), "+f"(d[17]), "+f"(d[18]), "+f"(d[19]), "+f"(d[20]), "+f"(d[21]), "+f"(d[22]), "+f"(d[23]), "+f"(d[24]), "+f"(d[25]), "+f"(d[26]), "+f"(d[27]), "+f"(d[28]), "+f"(d[29]), "+f"(d[30]), "+f"(d[31]), "+f"(d[32]), "+f"(d[33]), "+f"(d[34]), "+f"(d[35]), "+f"(d[36]), "+f"(d[37]), "+f"(d[38]), "+f"(d[39]), "+f"(d[40]), "+f"(d[41]), "+f"(d[42]), "+f"(d[43]), "+f"(d[44]), "+f"(d[45]), "+f"(d[46]), "+f"(d[47]), "+f"(d[48]), "+f"(d[49]), "+f"(d[50]), "+f"(d[51]), "+f"(d[52]), "+f"(d[53]), "+f"(d[54]), "+f"(d[55]), "+f"(d[56]), "+f"(d[57]), "+f"(d[58]), "+f"(d[59]), "+f"(d[60]), "+f"(d[61]), "+f"(d[62]), "+f"(d[63])
    : "r"(a0), "r"(a1), "r"(a2), "r"(a3), "l"(desc));
}
__device__ __forceinline__ void wg_rs_n24_acc(float (&d)[12], uint32_t a0, uint32_t a1, uint32_t a2, uint32_t a3, uint64_t desc) {
  asm volatile("{\n.reg .pred p;\nsetp.ne.b32 p, 1, 0;\n"
    "wgmma.mma_async.sync.aligned.m64n24k16.f32.bf16.bf16 {%0, %1, %2, %3, %4, %5, %6, %7, %8, %9, %10, %11}, {%12,%13,%14,%15}, %16, p, 1, 1, 0;\n}\n"
    : "+f"(d[0]), "+f"(d[1]), "+f"(d[2]), "+f"(d[3]), "+f"(d[4]), "+f"(d[5]), "+f"(d[6]), "+f"(d[7]), "+f"(d[8]), "+f"(d[9]), "+f"(d[10]), "+f"(d[11])
    : "r"(a0), "r"(a1), "r"(a2), "r"(a3), "l"(desc));
}
__device__ __forceinline__ void wg_ss_n256_t(float (&d)[128], uint64_t da, uint64_t db, int sc) {
  asm volatile("{\n.reg .pred p;\nsetp.ne.b32 p, %130, 0;\n"
    "wgmma.mma_async.sync.aligned.m64n256k16.f32.bf16.bf16 {%0, %1, %2, %3, %4, %5, %6, %7, %8, %9, %10, %11, %12, %13, %14, %15, %16, %17, %18, %19, %20, %21, %22, %23, %24, %25, %26, %27, %28, %29, %30, %31, %32, %33, %34, %35, %36, %37, %38, %39, %40, %41, %42, %43, %44, %45, %46, %47, %48, %49, %50, %51, %52, %53, %54, %55, %56, %57, %58, %59, %60, %61, %62, %63, %64, %65, %66, %67, %68, %69, %70, %71, %72, %73, %74, %75, %76, %77, %78, %79, %80, %81, %82, %83, %84, %85, %86, %87, %88, %89, %90, %91, %92, %93, %94, %95, %96, %97, %98, %99, %100, %101, %102, %103, %104, %105, %106, %107, %108, %109, %110, %111, %112, %113, %114, %115, %116, %117, %118, %119, %120, %121, %122, %123, %124, %125, %126, %127}, %128, %129, p, 1, 1, 0, 1;\n}\n"
    : "+f"(d[0]), "+f"(d[1]), "+f"(d[2]), "+f"(d[3]), "+f"(d[4]), "+f"(d[5]), "+f"(d[6]), "+f"(d[7]), "+f"(d[8]), "+f"(d[9]), "+f"(d[10]), "+f"(d[11]), "+f"(d[12]), "+f"(d[13]), "+f"(d[14]), "+f"(d[15]), "+f"(d[16]), "+f"(d[17]), "+f"(d[18]), "+f"(d[19]), "+f"(d[20]), "+f"(d[21]), "+f"(d[22]), "+f"(d[23]), "+f"(d[24]), "+f"(d[25]), "+f"(d[26]), "+f"(d[27]), "+f"(d[28]), "+f"(d[29]), "+f"(d[30]), "+f"(d[31]), "+f"(d[32]), "+f"(d[33]), "+f"(d[34]), "+f"(d[35]), "+f"(d[36]), "+f"(d[37]), "+f"(d[38]), "+f"(d[39]), "+f"(d[40]), "+f"(d[41]), "+f"(d[42]), "+f"(d[43]), "+f"(d[44]), "+f"(d[45]), "+f"(d[46]), "+f"(d[47]), "+f"(d[48]), "+f"(d[49]), "+f"(d[50]), "+f"(d[51]), "+f"(d[52]), "+f"(d[53]), "+f"(d[54]), "+f"(d[55]), "+f"(d[56]), "+f"(d[57]), "+f"(d[58]), "+f"(d[59]), "+f"(d[60]), "+f"(d[61]), "+f"(d[62]), "+f"(d[63]), "+f"(d[64]), "+f"(d[65]), "+f"(d[66]), "+f"(d[67]), "+f"(d[68]), "+f"(d[69]), "+f"(d[70]), "+f"(d[71]), "+f"(d[72]), "+f"(d[73]), "+f"(d[74]), "+f"(d[75]), "+f"(d[76]), "+f"(d[77]), "+f"(d[78]), "+f"(d[79]), "+f"(d[80]), "+f"(d[81]), "+f"(d[82]), "+f"(d[83]), "+f"(d[84]), "+f"(d[85]), "+f"(d[86]), "+f"(d[87]), "+f"(d[88]), "+f"(d[89]), "+f"(d[90]), "+f"(d[91]), "+f"(d[92]), "+f"(d[93]), "+f"(d[94]), "+f"(d[95]), "+f"(d[96]), "+f"(d[97]), "+f"(d[98]), "+f"(d[99]), "+f"(d[100]), "+f"(d[101]), "+f"(d[102]), "+f"(d[103]), "+f"(d[104]), "+f"(d[105]), "+f"(d[106]), "+f"(d[107]), "+f"(d[108]), "+f"(d[109]), "+f"(d[110]), "+f"(d[111]), "+f"(d[112]), "+f"(d[113]), "+f"(d[114]), "+f"(d[115]), "+f"(d[116]), "+f"(d[117]), "+f"(d[118]), "+f"(d[119]), "+f"(d[120]), "+f"(d[121]), "+f"(d[122]), "+f"(d[123]), "+f"(d[124]), "+f"(d[125]), "+f"(d[126]), "+f"(d[127])
    : "l"(da), "l"(db), "r"(sc));
}
__device__ __forceinline__ void wg_ss_n80(float (&d)[40], uint64_t da, uint64_t db, int sc) {
  asm volatile("{\n.reg .pred p;\nsetp.ne.b32 p, %42, 0;\n"
    "wgmma.mma_async.sync.aligned.m64n80k16.f32.bf16.bf16 {%0, %1, %2, %3, %4, %5, %6, %7, %8, %9, %10, %11, %12, %13, %14, %15, %16, %17, %18, %19, %20, %21, %22, %23, %24, %25, %26, %27, %28, %29, %30, %31, %32, %33, %34, %35, %36, %37, %38, %39}, %40, %41, p, 1, 1, 0, 0;\n}\n"
    : "+f"(d[0]), "+f"(d[1]), "+f"(d[2]), "+f"(d[3]), "+f"(d[4]), "+f"(d[5]), "+f"(d[6]), "+f"(d[7]), "+f"(d[8]), "+f"(d[9]), "+f"(d[10]), "+f"(d[11]), "+f"(d[12]), "+f"(d[13]), "+f"(d[14]), "+f"(d[15]), "+f"(d[16]), "+f"(d[17]), "+f"(d[18]), "+f"(d[19]), "+f"(d[20]), "+f"(d[21]), "+f"(d[22]), "+f"(d[23]), "+f"(d[24]), "+f"(d[25]), "+f"(d[26]), "+f"(d[27]), "+f"(d[28]), "+f"(d[29]), "+f"(d[30]), "+f"(d[31]), "+f"(d[32]), "+f"(d[33]), "+f"(d[34]), "+f"(d[35]), "+f"(d[36]), "+f"(d[37]), "+f"(d[38]), "+f"(d[39])
    : "l"(da), "l"(db), "r"(sc));
}
__device__ __forceinline__ void wg_ss_n128(float (&d)[64], uint64_t da, uint64_t db, int sc) {
  asm volatile("{\n.reg .pred p;\nsetp.ne.b32 p, %66, 0;\n"
    "wgmma.mma_async.sync.aligned.m64n128k16.f32.bf16.bf16 {%0, %1, %2, %3, %4, %5, %6, %7, %8, %9, %10, %11, %12, %13, %14, %15, %16, %17, %18, %19, %20, %21, %22, %23, %24, %25, %26, %27, %28, %29, %30, %31, %32, %33, %34, %35, %36, %37, %38, %39, %40, %41, %42, %43, %44, %45, %46, %47, %48, %49, %50, %51, %52, %53, %54, %55, %56, %57, %58, %59, %60, %61, %62, %63}, %64, %65, p, 1, 1, 0, 0;\n}\n"
    : "+f"(d[0]), "+f"(d[1]), "+f"(d[2]), "+f"(d[3]), "+f"(d[4]), "+f"(d[5]), "+f"(d[6]), "+f"(d[7]), "+f"(d[8]), "+f"(d[9]), "+f"(d[10]), "+f"(d[11]), "+f"(d[12]), "+f"(d[13]), "+f"(d[14]), "+f"(d[15]), "+f"(d[16]), "+f"(d[17]), "+f"(d[18]), "+f"(d[19]), "+f"(d[20]), "+f"(d[21]), "+f"(d[22]), "+f"(d[23]), "+f"(d[24]), "+f"(d[25]), "+f"(d[26]), "+f"(d[27]), "+f"(d[28]), "+f"(d[29]), "+f"(d[30]), "+f"(d[31]), "+f"(d[32]), "+f"(d[33]), "+f"(d[34]), "+f"(d[35]), "+f"(d[36]), "+f"(d[37]), "+f"(d[38]), "+f"(d[39]), "+f"(d[40]), "+f"(d[41]), "+f"(d[42]), "+f"(d[43]), "+f"(d[44]), "+f"(d[45]), "+f"(d[46]), "+f"(d[47]), "+f"(d[48]), "+f"(d[49]), "+f"(d[50]), "+f"(d[51]), "+f"(d[52]), "+f"(d[53]), "+f"(d[54]), "+f"(d[55]), "+f"(d[56]), "+f"(d[57]), "+f"(d[58]), "+f"(d[59]), "+f"(d[60]), "+f"(d[61]), "+f"(d[62]), "+f"(d[63])
    : "l"(da), "l"(db), "r"(sc));
}
__device__ __forceinline__ void wg_ss_n64(float (&d)[32], uint64_t da, uint64_t db, int sc) {
  asm volatile("{\n.reg .pred p;\nsetp.ne.b32 p, %34, 0;\n"
    "wgmma.mma_async.sync.aligned.m64n64k16.f32.bf16.bf16 {%0, %1, %2, %3, %4, %5, %6, %7, %8, %9, %10, %11, %12, %13, %14, %15, %16, %17, %18, %19, %20, %21, %22, %23, %24, %25, %26, %27, %28, %29, %30, %31}, %32, %33, p, 1, 1, 0, 0;\n}\n"
    : "+f"(d[0]), "+f"(d[1]), "+f"(d[2]), "+f"(d[3]), "+f"(d[4]), "+f"(d[5]), "+f"(d[6]), "+f"(d[7]), "+f"(d[8]), "+f"(d[9]), "+f"(d[10]), "+f"(d[11]), "+f"(d[12]), "+f"(d[13]), "+f"(d[14]), "+f"(d[15]), "+f"(d[16]), "+f"(d[17]), "+f"(d[18]), "+f"(d[19]), "+f"(d[20]), "+f"(d[21]), "+f"(d[22]), "+f"(d[23]), "+f"(d[24]), "+f"(d[25]), "+f"(d[26]), "+f"(d[27]), "+f"(d[28]), "+f"(d[29]), "+f"(d[30]), "+f"(d[31])
    : "l"(da), "l"(db), "r"(sc));
}
constexpr int ATT_H = 96;
template <int MODE>
__device__ __forceinline__ uint32_t exp2_pair_sw(float x0, float x1, uint32_t& det) {
  const float sc = __uint_as_float(0x00000100u);
  const float off = __uint_as_float(0x00007F00u);
  float r0, r1; uint32_t u, y, f, t, z;
  if (MODE == 0) {
    asm("fma.rn.f32 %0, %1, %2, %3;" : "=f"(r0) : "f"(x0), "f"(sc), "f"(off));
    asm("fma.rn.f32 %0, %1, %2, %3;" : "=f"(r1) : "f"(x1), "f"(sc), "f"(off));
    asm("cvt.pack.sat.u16.s32 %0, %1, %2;" : "=r"(u) : "r"(__float_as_uint(r1)), "r"(__float_as_uint(r0)));
  } else {
    asm("fma.rn.sat.f32 %0, %1, %2, %3;" : "=f"(r0) : "f"(x0), "f"(sc), "f"(off));
    asm("fma.rn.sat.f32 %0, %1, %2, %3;" : "=f"(r1) : "f"(x1), "f"(sc), "f"(off));
    det = __vimax3_u32(det, __float_as_uint(r0), __float_as_uint(r1));
    asm("prmt.b32 %0, %1, %2, 0x5410;" : "=r"(u) : "r"(__float_as_uint(r0)), "r"(__float_as_uint(r1)));
  }
  asm("lop3.b32 %0, %1, 0x00FF00FF, 0x44004400, 0xEA;" : "=r"(y) : "r"(u));
  asm("add.rn.f16x2 %0, %1, %2;" : "=r"(f) : "r"(y), "r"(0xC480C480u));
  asm("fma.rn.f16x2 %0, %1, %2, %3;" : "=r"(t) : "r"(f), "r"(0x2D092D09u), "r"(0x357E357Eu));
  asm("fma.rn.f16x2 %0, %1, %2, %3;" : "=r"(t) : "r"(t), "r"(f), "r"(0x3BD83BD8u));
  asm("fma.rn.f16x2 %0, %1, %2, %3;" : "=r"(z) : "r"(t), "r"(f), "r"(0x48354835u));
  uint32_t s = u >> 1, res;
  asm("lop3.b32 %0, %1, %2, 0x7F807F80, 0xE4;" : "=r"(res) : "r"(s), "r"(z));
  return res;
}
template <int EMU>
__device__ __forceinline__ void softmax_half(const float (&S)[32], uint32_t (&P)[16]) {
  uint32_t det;
#pragma unroll
  for (int i = 0; i < 16; i++) {
    if ((EMU >> i) & 1) P[i] = exp2_pair_sw<0>(S[2 * i], S[2 * i + 1], det);
    else P[i] = pack_bf16(ex2(S[2 * i]), ex2(S[2 * i + 1]));
  }
}
__device__ __forceinline__ void set_mparts(float m, int t, uint32_t& qb) {
  float nm = -m;
  float hi = __bfloat162float(__float2bfloat16_rn(nm)); float r = nm - hi;
  float mid = __bfloat162float(__float2bfloat16_rn(r)); float lo = r - mid;
  if (t == 2) qb = pack_bf16(hi, mid);
  if (t == 3) qb = pack_bf16(lo, 0.f);
}

__device__ __forceinline__ uint64_t dsc(uint32_t lo) { return ((uint64_t)16 << 32) | lo; }
template <int INC> __device__ __forceinline__ void dadd(uint64_t& d) {
  asm volatile("{\n.reg .b32 a, b;\nmov.b64 {a, b}, %0;\nadd.s32 a, a, %1;\nmov.b64 %0, {a, b};\n}" : "+l"(d) : "n"(INC));
}
__device__ __forceinline__ void qk_run(float (&S)[32], const uint32_t (&qa)[4], uint32_t b0, uint32_t b1, uint32_t z, uint64_t dA, uint64_t dB) {
  wg_rs_n64_first(S, qa[0], qa[1], qa[2], qa[3], dA); wg_rs_n64_acc(S, b0, b1, z, z, dB);
}
__device__ __forceinline__ void pv_run(float (&O)[12], const uint32_t (&P)[16], uint64_t (&dv)[4]) {
#pragma unroll
  for (int kk = 0; kk < 4; kk++) { wg_rs_n24_acc(O, P[4 * kk], P[4 * kk + 1], P[4 * kk + 2], P[4 * kk + 3], dv[kk]); dadd<192>(dv[kk]); }
}
__device__ __forceinline__ void att_s_tile(float (&c)[4], uint32_t ka, uint32_t kb, const uint32_t (&qa)[4], uint32_t qb0, uint32_t qb1) {
  uint32_t b0, b1, b2;
  asm volatile("ld.shared.b32 %0, [%1];" : "=r"(b0) : "r"(ka));
  asm volatile("ld.shared.b32 %0, [%1+128];" : "=r"(b1) : "r"(ka));
  asm volatile("ld.shared.b32 %0, [%1];" : "=r"(b2) : "r"(kb));
  c[0] = c[1] = c[2] = c[3] = 0.f;
  asm volatile("mma.sync.aligned.m16n8k16.row.col.f32.bf16.bf16.f32 {%0,%1,%2,%3}, {%4,%5,%6,%7}, {%8,%9}, {%0,%1,%2,%3};"
    : "+f"(c[0]), "+f"(c[1]), "+f"(c[2]), "+f"(c[3]) : "r"(qa[0]), "r"(qa[1]), "r"(qa[2]), "r"(qa[3]), "r"(b0), "r"(b1));
  asm volatile("mma.sync.aligned.m16n8k16.row.col.f32.bf16.bf16.f32 {%0,%1,%2,%3}, {%4,%5,%6,%7}, {%8,%9}, {%0,%1,%2,%3};"
    : "+f"(c[0]), "+f"(c[1]), "+f"(c[2]), "+f"(c[3]) : "r"(qb0), "r"(qb1), "r"(0u), "r"(0u), "r"(b2), "r"(0u));
}
template <int ID> __device__ __forceinline__ int wg_any(int v) {
  int r; asm volatile("{\n.reg .pred p, q;\nsetp.ne.s32 p, %1, 0;\nbar.red.or.pred q, %2, 128, p;\nselp.s32 %0, 1, 0, q;\n}" : "=r"(r) : "r"(v), "n"(ID) : "memory");
  return r;
}
constexpr int ATT_SMEM = 196608 + 128;
#define EMUV 0x4949
constexpr int ATT_EMU = EMUV;
__global__ void __maxnreg__(96) attn_kernel(const bf16* __restrict__ q, const uint8_t* __restrict__ kimg, const uint8_t* __restrict__ vimg, bf16* __restrict__ o) {
  extern __shared__ __align__(1024) uint8_t smem[];
  const uint32_t ks = smem_u32(smem), vs = ks + 98304, bars = ks + 196608;
  const int tid = threadIdx.x, lane = tid & 31, wg = tid >> 7, warp = (tid >> 5) & 3, g = lane >> 2, t = lane & 3;
  if (tid == 0) {
    for (int i = 0; i < 8; i++) mbar_init(bars + 8 * i, 1);
    asm volatile("fence.mbarrier_init.release.cluster;" ::: "memory");
  }
  __syncthreads();
  TL(5)
  pdl_wait();
  TL(6)
  if (tid == 0) {
    for (int i = 0; i < 8; i++) {
      mbar_expect_tx(bars + 8 * i, 24576);
      bulk_g2s(ks + i * 12288, kimg + i * 12288, 12288, bars + 8 * i);
      bulk_g2s(vs + i * 12288, vimg + i * 12288, 12288, bars + 8 * i);
    }
  }
  pdl_launch();
  const uint32_t kA = (ks >> 4) | (8u << 16), kB = ((ks + 8192) >> 4), vlo = (vs >> 4) | (8u << 16);
  uint32_t zr; asm volatile("mov.u32 %0, 0;" : "=r"(zr));
#pragma unroll 1
  for (int u = 0; u < 2; u++) {
    const int row0 = (blockIdx.x * 8 + wg * 2 + u) * 64 + warp * 16 + g;
    const bf16* q0 = q + (size_t)row0 * 20; const bf16* q1 = q0 + 160;
    uint32_t qa[4], qb0 = 0, qb1 = 0;
    qa[0] = *(const uint32_t*)(q0 + 2 * t); qa[1] = *(const uint32_t*)(q1 + 2 * t);
    qa[2] = *(const uint32_t*)(q0 + 8 + 2 * t); qa[3] = *(const uint32_t*)(q1 + 8 + 2 * t);
    if (t < 2) { qb0 = *(const uint32_t*)(q0 + 16 + 2 * t); qb1 = *(const uint32_t*)(q1 + 16 + 2 * t); }
    float O[12], l0, l1;
#pragma unroll 1
    for (int attempt = 0; attempt < 2; attempt++) {
      float S[32], tm0 = -INFINITY, tm1 = -INFINITY; uint32_t P[16];
      if (attempt) {
        set_mparts(0.f, t, qb0); set_mparts(0.f, t, qb1);
#pragma unroll 4
        for (int i = 0; i < 256; i++) {
          const uint32_t kb = ks + (i >> 5) * 12288 + (i & 15) * 256 + g * 16 + t * 4, par = (i >> 4) & 1;
          float c[4]; att_s_tile(c, kb + par * 4096, kb + 8192 + par * 128, qa, qb0, qb1);
          tm0 = fmaxf(tm0, fmaxf(c[0], c[1])); tm1 = fmaxf(tm1, fmaxf(c[2], c[3]));
        }
      }
      uint64_t dA = dsc(kA), dB = dsc(kB), dv[4];
#pragma unroll
      for (int i = 0; i < 4; i++) dv[i] = dsc(vlo + i * 48);
#pragma unroll
      for (int i = 0; i < 12; i++) O[i] = 0.f;
      if (u == 0) mbar_wait(bars, 0);
      wg_fence(); qk_run(S, qa, qb0, qb1, zr, dA, dB); wg_commit(); wg_wait<0>(); reg_fence(S);
      {
        float a = fmaxf(S[0], tm0), b = fmaxf(S[2], tm1);
#pragma unroll
        for (int i = 0; i < 8; i++) { a = fmaxf(a, fmaxf(S[4 * i], S[4 * i + 1])); b = fmaxf(b, fmaxf(S[4 * i + 2], S[4 * i + 3])); }
        a = fmaxf(a, __shfl_xor_sync(~0u, a, 1)); a = fmaxf(a, __shfl_xor_sync(~0u, a, 2));
        b = fmaxf(b, __shfl_xor_sync(~0u, b, 1)); b = fmaxf(b, __shfl_xor_sync(~0u, b, 2));
        const float m0 = ceilf(a) + (float)ATT_H, m1 = ceilf(b) + (float)ATT_H;
        set_mparts(m0, t, qb0); set_mparts(m1, t, qb1);
#pragma unroll
        for (int i = 0; i < 32; i++) S[i] -= ((i >> 1) & 1) ? m1 : m0;
      }
#define ATT_HALF(IA, IB)                                                                          \
      {                                                                                           \
        softmax_half<ATT_EMU>(S, P);                                                              \
        wg_fence();                                                                               \
        dadd<IA>(dA); dadd<IB>(dB); qk_run(S, qa, qb0, qb1, zr, dA, dB);                          \
        pv_run(O, P, dv); wg_commit();                                                            \
        wg_wait<0>(); reg_fence(S); reg_fence(O);                                                 \
      }
#pragma unroll 1
      for (int pr = 0; pr < 8; pr++) {
        ATT_HALF(128, 128)
        ATT_HALF(128, -120)
        ATT_HALF(128, 128)
        if (u == 0 && pr < 7) mbar_wait(bars + 8 * (pr + 1), 0);
        ATT_HALF(384, 632)
      }
      l0 = __shfl_sync(~0u, O[8], (lane & ~3) | 2); l1 = __shfl_sync(~0u, O[10], (lane & ~3) | 2);
      int ok = (l0 < 4.2535296e37f) && (l1 < 4.2535296e37f);
#pragma unroll
      for (int i = 0; i < 12; i++) ok &= (fabsf(O[i]) <= 3.4e38f);
      int bad;
      if (wg == 0) bad = wg_any<1>(!ok); else if (wg == 1) bad = wg_any<2>(!ok); else if (wg == 2) bad = wg_any<3>(!ok); else bad = wg_any<4>(!ok);
      if (!bad) break;
    }
    const float i0 = 1.f / l0, i1 = 1.f / l1;
    bf16* o0 = o + (size_t)row0 * 20; bf16* o1 = o0 + 160;
    *(uint32_t*)(o0 + 2 * t) = pack_bf16(O[0] * i0, O[1] * i0); *(uint32_t*)(o1 + 2 * t) = pack_bf16(O[2] * i1, O[3] * i1);
    *(uint32_t*)(o0 + 8 + 2 * t) = pack_bf16(O[4] * i0, O[5] * i0); *(uint32_t*)(o1 + 8 + 2 * t) = pack_bf16(O[6] * i1, O[7] * i1);
    if (t < 2) { *(uint32_t*)(o0 + 16 + 2 * t) = pack_bf16(O[8] * i0, O[9] * i0); *(uint32_t*)(o1 + 16 + 2 * t) = pack_bf16(O[10] * i1, O[11] * i1); }
  }
  TL(7)
}
__device__ __align__(1024) bf16 g_xn[2048 * 640];
__device__ __align__(1024) bf16 g_wkv[640 * 64];
__device__ __align__(1024) bf16 g_wT[640 * 2176];
__device__ __align__(1024) bf16 g_q[2048 * 640];
__device__ __align__(1024) bf16 g_o[2048 * 640];
__device__ __align__(1024) bf16 g_h[2048 * 1536];
__device__ __align__(1024) bf16 g_y[2048 * 640];
__device__ __align__(1024) bf16 g_kimg[2048 * 24];
__device__ __align__(1024) bf16 g_vimg[2048 * 24];

__global__ void __launch_bounds__(256, 4) prep_kernel(const bf16* __restrict__ x, const bf16* __restrict__ wk, const bf16* __restrict__ wv,
    const bf16* wq, const bf16* wg, const bf16* wu, const bf16* wd, const bf16* wo) {
  TL(0)
  pdl_launch();
  const int tid = threadIdx.x, lane = tid & 31, b = blockIdx.x;
  const int row0 = b * 16 + (tid >> 5) * 2;
  uint2 v[2][5];
#pragma unroll
  for (int rr = 0; rr < 2; rr++)
#pragma unroll
    for (int i = 0; i < 5; i++) v[rr][i] = ((const uint2*)(x + (size_t)(row0 + rr) * 640))[lane + 32 * i];
  for (int i = b * 256 + tid; i < 640 * 64; i += 128 * 256) {
    const int k = i >> 6, c = i & 63;
    g_wkv[i] = c < 20 ? wk[k * 20 + c] : (c >= 32 && c < 52) ? wv[k * 20 + c - 32] : __float2bfloat16(0.f);
  }
#pragma unroll
  for (int rr = 0; rr < 2; rr++) {
    float f[20], s = 0.f;
#pragma unroll
    for (int i = 0; i < 5; i++) {
      f[4 * i] = __uint_as_float(v[rr][i].x << 16); f[4 * i + 1] = __uint_as_float(v[rr][i].x & 0xFFFF0000u);
      f[4 * i + 2] = __uint_as_float(v[rr][i].y << 16); f[4 * i + 3] = __uint_as_float(v[rr][i].y & 0xFFFF0000u);
      s += (f[4 * i] + f[4 * i + 1]) + (f[4 * i + 2] + f[4 * i + 3]);
    }
#pragma unroll
    for (int o = 16; o; o >>= 1) s += __shfl_xor_sync(~0u, s, o);
    const float mean = s * (1.f / 640.f), mb = __bfloat162float(__float2bfloat16(mean));
    float ss = 0.f;
#pragma unroll
    for (int i = 0; i < 20; i++) { const float d = f[i] - mean; ss = fmaf(d, d, ss); f[i] = __bfloat162float(__float2bfloat16(f[i] - mb)); }
#pragma unroll
    for (int o = 16; o; o >>= 1) ss += __shfl_xor_sync(~0u, ss, o);
    const float vb = __bfloat162float(__float2bfloat16(ss * (1.f / 640.f)));
    const float r = 1.f / __bfloat162float(__float2bfloat16(sqrtf(__bfloat162float(__float2bfloat16(vb + 1e-5f)))));
    uint2* dst = (uint2*)(g_xn + (size_t)(row0 + rr) * 640);
#pragma unroll
    for (int i = 0; i < 5; i++) dst[lane + 32 * i] = make_uint2(pack_bf16(f[4 * i] * r, f[4 * i + 1] * r), pack_bf16(f[4 * i + 2] * r, f[4 * i + 3] * r));
  }
}
__device__ __forceinline__ void transpose_task(int w, int lane, const bf16* __restrict__ wo, const bf16* __restrict__ wd) {
  const int k0 = (w / 10) * 32 + (lane >> 3) * 8, n0 = (w % 10) * 64 + (lane & 7) * 8;
  const bf16* src = k0 < 1536 ? wd + (size_t)k0 * 640 + n0 : wo + (size_t)(k0 - 1536) * 640 + n0;
  uint32_t r[8][4];
#pragma unroll
  for (int i = 0; i < 8; i++) { uint4 u = __ldg((const uint4*)(src + (size_t)i * 640)); r[i][0] = u.x; r[i][1] = u.y; r[i][2] = u.z; r[i][3] = u.w; }
#pragma unroll
  for (int j = 0; j < 8; j++) {
    uint32_t o[4];
#pragma unroll
    for (int w2 = 0; w2 < 4; w2++) o[w2] = __byte_perm(r[2 * w2][j >> 1], r[2 * w2 + 1][j >> 1], (j & 1) ? 0x7632 : 0x5410);
    *(uint4*)(g_wT + (size_t)(n0 + j) * 2176 + k0) = make_uint4(o[0], o[1], o[2], o[3]);
  }
}

constexpr int K1_STB = 49152, K1_STG = 4 * K1_STB, K1_SMEM = K1_STG + 8 * 4352 + 128;
__device__ __forceinline__ void warp_store128(uint32_t stg, const uint32_t (&w)[32], int lane, bf16* gptr, int ld) {
  const uint32_t wa = stg + ((lane & 7) + (lane & 8)) * 272 + (lane >> 4) * 16;
#pragma unroll
  for (int i = 0; i < 8; i++)
    asm volatile("stmatrix.sync.aligned.m8n8.x4.shared.b16 [%0], {%1,%2,%3,%4};" :: "r"(wa + i * 32), "r"(w[4 * i]), "r"(w[4 * i + 1]), "r"(w[4 * i + 2]), "r"(w[4 * i + 3]) : "memory");
  __syncwarp();
  const int rr = lane >> 4, cc = lane & 15;
#pragma unroll
  for (int i = 0; i < 8; i++) {
    uint4 v; asm volatile("ld.shared.v4.b32 {%0,%1,%2,%3}, [%4];" : "=r"(v.x), "=r"(v.y), "=r"(v.z), "=r"(v.w) : "r"(stg + (2 * i + rr) * 272 + cc * 16));
    *(uint4*)(gptr + (size_t)(2 * i + rr) * ld + cc * 8) = v;
  }
  __syncwarp();
}
__device__ __forceinline__ float gelu_mul(float g, float u) {
  const float z = g * fmaf(g * g, 0.044715f * 0.7978845608f, 0.7978845608f);
  float th; asm("tanh.approx.f32 %0, %1;" : "=f"(th) : "f"(z));
  const float hg = 0.5f * g;
  return fmaf(hg, th, hg) * u;
}
__global__ void __cluster_dims__(2, 1, 1) __launch_bounds__(320, 1) proj_kernel(const __grid_constant__ CUtensorMap tmx, const __grid_constant__ CUtensorMap tmg,
    const __grid_constant__ CUtensorMap tmu, const __grid_constant__ CUtensorMap tmq, const __grid_constant__ CUtensorMap tmkv,
    const bf16* __restrict__ wo, const bf16* __restrict__ wd) {
  extern __shared__ __align__(1024) uint8_t smem[];
  const uint32_t s0 = smem_u32(smem), bF = s0 + K1_STG + 8 * 4352, bE = bF + 32;
  const int tid = threadIdx.x, lane = tid & 31, wg = tid >> 7;
  const int rank = blockIdx.x & 1, mt = (blockIdx.x >> 4) * 2 + rank, j = (blockIdx.x >> 1) & 7;
  const int npass = j == 7 ? 1 : 2;
  if (tid == 0) {
    for (int i = 0; i < 4; i++) { mbar_init(bF + 8 * i, 1); mbar_init(bE + 8 * i, 16); }
    asm volatile("fence.mbarrier_init.release.cluster;" ::: "memory");
  }
  TL(1)
  cluster_sync();
  pdl_launch();
  if (tid >= 288) {
#pragma unroll 1
    for (int w = blockIdx.x; w < 680; w += 128) transpose_task(w, lane, wo, wd);
  } else if (wg == 2) {
    if (lane == 0) {
      const int nit = npass * 10;
      if (j == 7) pdl_wait();
      for (int it = 0; it < nit; it++) {
        const int s = it & 3, p = it >= 10, slot = 2 * j + p, k0 = (it - 10 * p) * 64;
        if (it >= 4) mbar_wait(bE + 8 * s, ((it >> 2) - 1) & 1);
        const uint32_t dst = s0 + s * K1_STB + 16384 + rank * 16384, fb = bF + 8 * s;
        mbar_expect_tx(fb, slot == 14 ? 40960 : 49152);
        if (slot < 12) {
          const CUtensorMap* tm = rank ? &tmu : &tmg;
          tma2d_mc(dst, tm, slot * 128, k0, fb); tma2d_mc(dst + 8192, tm, slot * 128 + 64, k0, fb);
        } else if (slot < 14) {
          const int c0 = (slot - 12) * 256 + rank * 128;
          tma2d_mc(dst, &tmq, c0, k0, fb); tma2d_mc(dst + 8192, &tmq, c0 + 64, k0, fb);
        } else if (rank == 0) { tma2d_mc(dst, &tmq, 512, k0, fb); tma2d_mc(dst + 8192, &tmq, 576, k0, fb); }
        else tma2d_mc(dst, &tmkv, 0, k0, fb);
        if (it >= 4) tma2d(s0 + s * K1_STB, &tmx, k0, mt * 128, fb);
        else if (it == 3) {
          pdl_wait();
          for (int i = 0; i < 4; i++) tma2d(s0 + i * K1_STB, &tmx, i * 64, mt * 128, bF + 8 * i);
        }
      }
    }
  } else {
  const int warp = (tid >> 5) & 3, g = lane >> 2, t = lane & 3;
  const int rw = mt * 128 + wg * 64 + warp * 16, r0 = rw + g;
  const uint32_t stg = s0 + K1_STG + (tid >> 5) * 4352;
  int it = 0;
  for (int p = 0; p < npass; p++) {
    const int slot = 2 * j + p;
    float acc[128];
#pragma unroll
    for (int i = 0; i < 128; i++) acc[i] = 0.f;
#pragma unroll 1
    for (int kb = 0; kb < 10; kb++, it++) {
      const int s = it & 3;
      mbar_wait(bF + 8 * s, (it >> 2) & 1);
      wg_fence();
      const uint32_t a = s0 + s * K1_STB + wg * 8192, b = s0 + s * K1_STB + 16384;
#pragma unroll
      for (int k = 0; k < 4; k++) wg_ss_n256_t(acc, mk_desc(a + 32 * k, 16, 1024, 1), mk_desc(b + 2048 * k, 8192, 1024, 1), 1);
      wg_commit();
      if (kb > 0) { wg_wait<1>(); if (lane == 0 && it - 1 < npass * 10 - 4) mbar_arrive_both(bE + 8 * ((it - 1) & 3)); }
    }
    wg_wait<0>(); reg_fence(acc);
    TL(2 + p)
    if (lane == 0 && it - 1 < npass * 10 - 4) mbar_arrive_both(bE + 8 * ((it - 1) & 3));
    if (slot < 12) {
      uint32_t w[32];
#pragma unroll
      for (int i = 0; i < 16; i++) {
        w[2 * i] = pack_bf16(gelu_mul(acc[4 * i], acc[64 + 4 * i]), gelu_mul(acc[4 * i + 1], acc[65 + 4 * i]));
        w[2 * i + 1] = pack_bf16(gelu_mul(acc[4 * i + 2], acc[66 + 4 * i]), gelu_mul(acc[4 * i + 3], acc[67 + 4 * i]));
      }
      warp_store128(stg, w, lane, g_h + (size_t)rw * 1536 + slot * 128, 1536);
    } else {
      const float sc = 0.22360679775f * 1.4426950408889634f;
#pragma unroll
      for (int hh = 0; hh < 2; hh++)
        if (hh == 0 || slot != 14) {
          uint32_t w[32];
#pragma unroll
          for (int i = 0; i < 16; i++) {
            w[2 * i] = pack_bf16(acc[64 * hh + 4 * i] * sc, acc[64 * hh + 4 * i + 1] * sc);
            w[2 * i + 1] = pack_bf16(acc[64 * hh + 4 * i + 2] * sc, acc[64 * hh + 4 * i + 3] * sc);
          }
          warp_store128(stg, w, lane, g_q + (size_t)rw * 640 + (slot - 12) * 256 + hh * 128, 640);
        }
      if (slot == 14) {
#pragma unroll
        for (int hr = 0; hr < 2; hr++) {
          const int n = r0 + 8 * hr, tile = n >> 7, kg = (n & 127) >> 3, par = tile & 1;
#pragma unroll
          for (int c = 0; c < 3; c++) {
            float k0 = acc[64 + 4 * c + 2 * hr], k1 = acc[65 + 4 * c + 2 * hr], v0 = acc[80 + 4 * c + 2 * hr], v1 = acc[81 + 4 * c + 2 * hr];
            if (c == 2 && t >= 2) { k0 = 1.f; k1 = t == 2 ? 1.f : 0.f; v0 = t == 2 ? 1.f : 0.f; v1 = 0.f; }
            const int ko = (tile >> 1) * 6144 + (c < 2 ? par * 2048 + kg * 128 + c * 64 : 4096 + kg * 128 + par * 64) + (n & 7) * 8 + 2 * t;
            *(uint32_t*)(g_kimg + ko) = pack_bf16(k0, k1);
            const int vo = (n >> 4) * 384 + c * 128 + ((n >> 3) & 1) * 64 + 2 * t * 8 + (n & 7);
            g_vimg[vo] = __float2bfloat16(v0); g_vimg[vo + 8] = __float2bfloat16(v1);
          }
        }
      }
    }
  }
  TL(4)
  }
}

constexpr int DN_STB = 8192 + 5120, DN_ST = 2, DN_IT = 36, DN_SMEM = DN_ST * DN_STB + 64;
__global__ void __launch_bounds__(128) down_kernel(const __grid_constant__ CUtensorMap tmh, const __grid_constant__ CUtensorMap tmw, const bf16* __restrict__ x) {
  extern __shared__ __align__(1024) uint8_t smem[];
  const uint32_t s0 = smem_u32(smem), bF = s0 + DN_ST * DN_STB;
  const int tid = threadIdx.x, lane = tid & 31;
  const int mt = blockIdx.x >> 3, j = blockIdx.x & 7;
  if (tid == 0) {
    for (int i = 0; i < DN_ST; i++) mbar_init(bF + 8 * i, 1);
    asm volatile("fence.mbarrier_init.release.cluster;" ::: "memory");
  }
  __syncthreads();
  pdl_launch();
  auto fill = [&](int it, int s) {
    const uint32_t dst = s0 + s * DN_STB, fb = bF + 8 * s;
    mbar_expect_tx(fb, DN_STB);
    tma2d(dst, &tmh, it * 32, mt * 128, fb);
    tma2d(dst + 8192, &tmw, it * 32, j * 80, fb);
  };
  TL(8)
  if (tid == 0) for (int i = 0; i < DN_ST; i++) fill(i, i);
  {
    const int warp = tid >> 5, g = lane >> 2, t = lane & 3;
    float a0[40], a1[40];
#pragma unroll
    for (int i = 0; i < 40; i++) a0[i] = a1[i] = 0.f;
#pragma unroll 1
    for (int it = 0; it < DN_IT; it++) {
      const int s = it & 1;
      mbar_wait(bF + 8 * s, (it >> 1) & 1);
      wg_fence();
      const uint32_t a = s0 + s * DN_STB, b = a + 8192;
#pragma unroll
      for (int k = 0; k < 2; k++) {
        wg_ss_n80(a0, mk_desc(a + 32 * k, 16, 512, 2), mk_desc(b + 32 * k, 16, 512, 2), 1);
        wg_ss_n80(a1, mk_desc(a + 4096 + 32 * k, 16, 512, 2), mk_desc(b + 32 * k, 16, 512, 2), 1);
      }
      wg_commit(); wg_wait<0>();
      __syncthreads();
      if (tid == 0 && it + 2 < DN_IT) fill(it + 2, s);
    }
    reg_fence(a0); reg_fence(a1);
#pragma unroll
    for (int hh = 0; hh < 2; hh++) {
      const size_t off = (size_t)(mt * 128 + hh * 64 + warp * 16 + g) * 640 + j * 80 + 2 * t;
      const uint32_t* x0 = (const uint32_t*)(x + off); uint32_t* y0 = (uint32_t*)(g_y + off);
#pragma unroll
      for (int i = 0; i < 10; i++) {
        const uint32_t xa = __ldg(x0 + 4 * i), xb = __ldg(x0 + 8 * 320 + 4 * i);
        const float* ac = hh ? a1 : a0;
        y0[4 * i] = pack_bf16(ac[4 * i] + __uint_as_float(xa << 16), ac[4 * i + 1] + __uint_as_float(xa & 0xFFFF0000u));
        y0[8 * 320 + 4 * i] = pack_bf16(ac[4 * i + 2] + __uint_as_float(xb << 16), ac[4 * i + 3] + __uint_as_float(xb & 0xFFFF0000u));
      }
    }
  }
  TL(9)
  pdl_wait();
}

constexpr int K3_STB = 8192 + 20480, K3_SMEM = 8 * K3_STB + 256;
__global__ void __launch_bounds__(288, 1) out_kernel(const __grid_constant__ CUtensorMap tmh, const __grid_constant__ CUtensorMap tmo,
    const __grid_constant__ CUtensorMap tmw, bf16* __restrict__ out) {
  constexpr int K0 = 32 * DN_IT, NH = (1536 - K0) / 64, NIT = NH + 10;
  extern __shared__ __align__(1024) uint8_t smem[];
  const uint32_t s0 = smem_u32(smem), bF = s0 + 8 * K3_STB, bE = bF + 64;
  const int tid = threadIdx.x, lane = tid & 31, wg = tid >> 7;
  const int mt = blockIdx.x >> 2, j = blockIdx.x & 3;
  if (tid == 0) {
    for (int i = 0; i < 8; i++) mbar_init(bF + 8 * i, 1);
    for (int i = 0; i < 8; i++) mbar_init(bE + 8 * i, 8);
    asm volatile("fence.mbarrier_init.release.cluster;" ::: "memory");
  }
  __syncthreads();
  if (wg == 2) {
    if (lane == 0) {
      for (int it = 0; it < 8; it++) {
        mbar_expect_tx(bF + 8 * it, K3_STB); tma2d(s0 + it * K3_STB + 8192, &tmw, K0 + it * 64, j * 160, bF + 8 * it);
        if (it < NH) tma2d(s0 + it * K3_STB, &tmh, K0 + it * 64, mt * 64, bF + 8 * it);
      }
      pdl_wait();
      for (int it = NH; it < 8; it++) tma2d(s0 + it * K3_STB, &tmo, (it - NH) * 64, mt * 64, bF + 8 * it);
      for (int it = 8; it < NIT; it++) {
        const int s = it & 7;
        mbar_wait(bE + 8 * s, ((it >> 3) - 1) & 1);
        mbar_expect_tx(bF + 8 * s, K3_STB);
        if (it < NH) tma2d(s0 + s * K3_STB, &tmh, K0 + it * 64, mt * 64, bF + 8 * s); else tma2d(s0 + s * K3_STB, &tmo, (it - NH) * 64, mt * 64, bF + 8 * s);
        tma2d(s0 + s * K3_STB + 8192, &tmw, K0 + it * 64, j * 160, bF + 8 * s);
      }
    }
    return;
  }
  const int warp = (tid >> 5) & 3;
  const size_t off = (size_t)(mt * 64 + warp * 16) * 640 + j * 160 + wg * 80;
  float acc[40];
#pragma unroll
  for (int i = 0; i < 40; i++) acc[i] = 0.f;
  TL(10)
  pdl_wait();
  TL(11)
  uint4 yr[5];
#pragma unroll
  for (int i = 0; i < 5; i++) { const int c = lane + 32 * i, r = c / 10; yr[i] = *(const uint4*)(g_y + off + (size_t)r * 640 + (c - r * 10) * 8); }
#pragma unroll 1
  for (int it = 0; it < NIT; it++) {
    const int s = it & 7;
    mbar_wait(bF + 8 * s, (it >> 3) & 1);
    wg_fence();
    const uint32_t a = s0 + s * K3_STB, b = a + 8192 + wg * 10240;
#pragma unroll
    for (int k = 0; k < 4; k++) wg_ss_n80(acc, mk_desc(a + 32 * k, 16, 1024, 1), mk_desc(b + 32 * k, 16, 1024, 1), 1);
    wg_commit();
    if (it >= 1 && it <= NIT - 8) { wg_wait<1>(); if (lane == 0) mbar_arrive(bE + 8 * ((it - 1) & 7)); }
  }
  wg_wait<0>(); reg_fence(acc);
  TL(12)
  asm volatile("bar.sync 1, 256;" ::: "memory");
  const uint32_t stg = s0 + (tid >> 5) * (16 * 336);
  {
    const int g = lane >> 2, t = lane & 3;
#pragma unroll
    for (int i = 0; i < 10; i++) {
      asm volatile("st.shared.v2.f32 [%0], {%1,%2};" :: "r"(stg + g * 336 + i * 32 + t * 8), "f"(acc[4 * i]), "f"(acc[4 * i + 1]) : "memory");
      asm volatile("st.shared.v2.f32 [%0], {%1,%2};" :: "r"(stg + (g + 8) * 336 + i * 32 + t * 8), "f"(acc[4 * i + 2]), "f"(acc[4 * i + 3]) : "memory");
    }
  }
  __syncwarp();
#pragma unroll
  for (int i = 0; i < 5; i++) {
    const int c = lane + 32 * i, r = c / 10, cc = c - r * 10;
    float v[8];
    asm volatile("ld.shared.v4.f32 {%0,%1,%2,%3}, [%4];" : "=f"(v[0]), "=f"(v[1]), "=f"(v[2]), "=f"(v[3]) : "r"(stg + r * 336 + cc * 32));
    asm volatile("ld.shared.v4.f32 {%0,%1,%2,%3}, [%4];" : "=f"(v[4]), "=f"(v[5]), "=f"(v[6]), "=f"(v[7]) : "r"(stg + r * 336 + cc * 32 + 16));
    const uint32_t yy[4] = {yr[i].x, yr[i].y, yr[i].z, yr[i].w};
    uint32_t w[4];
#pragma unroll
    for (int k = 0; k < 4; k++) w[k] = pack_bf16(v[2 * k] + __uint_as_float(yy[k] << 16), v[2 * k + 1] + __uint_as_float(yy[k] & 0xFFFF0000u));
    *(uint4*)(out + off + (size_t)r * 640 + cc * 8) = make_uint4(w[0], w[1], w[2], w[3]);
  }
  TL(13)
}
typedef CUresult (*EncFn)(CUtensorMap*, CUtensorMapDataType, cuuint32_t, void*, const cuuint64_t*, const cuuint64_t*, const cuuint32_t*, const cuuint32_t*,
                          CUtensorMapInterleave, CUtensorMapSwizzle, CUtensorMapL2promotion, CUtensorMapFloatOOBfill);
static void mk_map(EncFn enc, CUtensorMap* m, const void* p, uint64_t cols, uint64_t rows, uint32_t bc, uint32_t br, CUtensorMapSwizzle sw = CU_TENSOR_MAP_SWIZZLE_128B) {
  cuuint64_t dims[2] = {cols, rows}, strides[1] = {cols * 2}; cuuint32_t box[2] = {bc, br}, es[2] = {1, 1};
  enc(m, CU_TENSOR_MAP_DATA_TYPE_BFLOAT16, 2, (void*)p, dims, strides, box, es, CU_TENSOR_MAP_INTERLEAVE_NONE, sw,
      CU_TENSOR_MAP_L2_PROMOTION_L2_256B, CU_TENSOR_MAP_FLOAT_OOB_FILL_NONE);
}
template <typename... KArgs, typename... Args>
static void launch(void (*k)(KArgs...), int grid, int block, int smem, cudaStream_t st, Args... args) {
  cudaLaunchConfig_t c = {}; c.gridDim = dim3(grid); c.blockDim = dim3(block); c.dynamicSmemBytes = smem; c.stream = st;
  cudaLaunchAttribute at[1]; at[0].id = cudaLaunchAttributeProgrammaticStreamSerialization; at[0].val.programmaticStreamSerializationAllowed = 1;
  c.attrs = at; c.numAttrs = 1;
  cudaLaunchKernelEx(&c, k, KArgs(args)...);
}
extern "C" void kernel_launch(void* const* d_in, const int* in_sizes, int n_in, void* d_out, int out_size) {
  const bf16* x = (const bf16*)d_in[0]; const bf16* wq = (const bf16*)d_in[1]; const bf16* wk = (const bf16*)d_in[2]; const bf16* wv = (const bf16*)d_in[3];
  const bf16* wo = (const bf16*)d_in[4]; const bf16* wg = (const bf16*)d_in[6]; const bf16* wu = (const bf16*)d_in[7]; const bf16* wd = (const bf16*)d_in[8];
  static bool init = false;
  CUtensorMap tmx, tmg, tmu, tmq, tmkv, tmh, tmo, tmw, tmw32, tmh64;
  void *p_q, *p_o, *p_k, *p_v;
  static EncFn enc;
  if (!init) {
    void* fn = nullptr; cudaDriverEntryPointQueryResult qr;
    cudaGetDriverEntryPoint("cuTensorMapEncodeTiled", &fn, cudaEnableDefault, &qr);
    enc = (EncFn)fn;
    cudaFuncSetAttribute(proj_kernel, cudaFuncAttributeMaxDynamicSharedMemorySize, K1_SMEM);
    cudaFuncSetAttribute(attn_kernel, cudaFuncAttributeMaxDynamicSharedMemorySize, ATT_SMEM);
    cudaFuncSetAttribute(out_kernel, cudaFuncAttributeMaxDynamicSharedMemorySize, K3_SMEM);
    cudaFuncSetAttribute(down_kernel, cudaFuncAttributePreferredSharedMemoryCarveout, 100);
    init = true;
  }
  {
    void *p_xn, *p_wkv, *p_wT, *p_h;
    cudaGetSymbolAddress(&p_xn, g_xn); cudaGetSymbolAddress(&p_wkv, g_wkv); cudaGetSymbolAddress(&p_wT, g_wT); cudaGetSymbolAddress(&p_h, g_h);
    cudaGetSymbolAddress(&p_q, g_q); cudaGetSymbolAddress(&p_o, g_o); cudaGetSymbolAddress(&p_k, g_kimg); cudaGetSymbolAddress(&p_v, g_vimg);
    mk_map(enc, &tmx, p_xn, 640, 2048, 64, 128);
    mk_map(enc, &tmg, wg, 1536, 640, 64, 64); mk_map(enc, &tmu, wu, 1536, 640, 64, 64);
    mk_map(enc, &tmq, wq, 640, 640, 64, 64); mk_map(enc, &tmkv, p_wkv, 64, 640, 64, 64);
    mk_map(enc, &tmh, p_h, 1536, 2048, 32, 128, CU_TENSOR_MAP_SWIZZLE_64B); mk_map(enc, &tmw32, p_wT, 2176, 640, 32, 80, CU_TENSOR_MAP_SWIZZLE_64B);
    mk_map(enc, &tmh64, p_h, 1536, 2048, 64, 64);
    mk_map(enc, &tmo, p_o, 640, 2048, 64, 64); mk_map(enc, &tmw, p_wT, 2176, 640, 64, 160);
  }
  cudaStream_t st = cudaStreamPerThread;
  launch(prep_kernel, 128, 256, 0, st, x, wk, wv, wq, wg, wu, wd, wo);
  launch(proj_kernel, 128, 320, K1_SMEM, st, tmx, tmg, tmu, tmq, tmkv, wo, wd);
  launch(attn_kernel, 128, 512, ATT_SMEM, st, (const bf16*)p_q, (const uint8_t*)p_k, (const uint8_t*)p_v, (bf16*)p_o);
  launch(down_kernel, 128, 128, DN_SMEM, st, tmh, tmw32, x);
  launch(out_kernel, 128, 288, K3_SMEM, st, tmh64, tmo, tmw, (bf16*)d_out);
}
```
